```python
import torch

def _softmax(x, axis=-1):
    return torch.softmax(x, dim=axis)
def _gelu(x):
    return torch.nn.functional.gelu(x, approximate="tanh")
def _silu(x):
    return torch.nn.functional.silu(x)
def _sigmoid(x):
    return torch.sigmoid(x)
def _layernorm(x, axis=-1, eps=1e-5):
    m = x.mean(dim=axis, keepdim=True)
    v = x.var(dim=axis, keepdim=True, unbiased=False)
    return (x - m) / torch.sqrt(v + eps)
def _scatter_add(tgt, idx, src, axis=0):
    return tgt.clone().index_add_(axis, idx, src)
def _segment_sum(src, seg, n):
    out = torch.zeros((n,) + src.shape[1:], dtype=src.dtype)
    return out.index_add_(0, seg, src)
def _pad(x, pw):
    flat = tuple(v for pair in reversed(pw) for v in pair)
    return torch.nn.functional.pad(x, flat)

kernel_name = 'gated_mix__sliding_block__dense_activation_silu__prompt'

def setup_inputs():

    _w = (lambda a: (lambda t: t.to(torch.bfloat16) if t.is_floating_point() else t)(torch.as_tensor(a)))
    def _A_setup():
        B, S, D = 1, 2048, 512
        return {
            "x": _w((lambda *s: torch.randn(*s, dtype=torch.bfloat16) * 0.1)(B, S, D)),
            "wqkv": _w((lambda *s: torch.randn(*s, dtype=torch.bfloat16) * 0.4)(D, 3 * D)),
            "wo": _w((lambda *s: torch.randn(*s, dtype=torch.bfloat16) * 0.1)(D, D)),
        }
    _A_in = _A_setup()

    def _B_setup():
        B, S, D, F = 1, 2048, 512, 1792
        return {
            "x": _w((lambda *s: torch.randn(*s, dtype=torch.bfloat16) * 0.1)(B, S, D)),
            "w1": _w((lambda *s: torch.randn(*s, dtype=torch.bfloat16) * 3.2)(D, F) * (D ** -0.5)),
            "w2": _w((lambda *s: torch.randn(*s, dtype=torch.bfloat16) * 3.2)(F, D) * (F ** -0.5)),
        }
    _B_in = _B_setup()

    return {
        "A_x": _A_in["x"],
        "A_wqkv": _A_in["wqkv"],
        "A_wo": _A_in["wo"],
        "B_x": _B_in["x"],
        "B_w1": _B_in["w1"],
        "B_w2": _B_in["w2"],
        "gate_w": _w((lambda *s: torch.randn(*s, dtype=torch.bfloat16) * 0.1)(512) * 16.0),
    }

def reference(A_x, A_wqkv, A_wo, B_x, B_w1, B_w2, gate_w):
    def _A_ref(x, wqkv, wo):
        B, S, D = x.shape
        H = 32; Dh = D // H; W = 256
        qkv = (lambda x, *d: x.permute(*d))((x @ wqkv).reshape(B, S, 3, H, Dh), 2, 0, 3, 1, 4)
        q, k, v = qkv[0], qkv[1], qkv[2]
        scores = torch.einsum("bhqd,bhkd->bhqk", q, k) * (Dh ** -0.5)
        idx = torch.arange(S)
        mask = (idx[:, None] - idx[None, :] >= 0) & (idx[:, None] - idx[None, :] < W)
        scores = torch.where(mask[None, None], scores, -1e9)
        p = _softmax(scores, axis=-1)
        o = torch.einsum("bhqk,bhkd->bhqd", p, v)
        return (lambda x, *d: x.permute(*d))(o, 0, 2, 1, 3).reshape(B, S, D) @ wo

    def _B_ref(x, w1, w2):
        h = torch.einsum("bsd,df->bsf", x, w1)
        h = _silu(h)
        out = torch.einsum("bsf,fd->bsd", h, w2)
        return out

    x = A_x
    g = _sigmoid((x * gate_w).sum(-1, keepdims=True))
    a = _A_ref(x, A_wqkv, A_wo)
    b = _B_ref(x, B_w1, B_w2)
    return g * a + (1 - g) * b
```

```cpp
#include <cuda_runtime.h>
#include <cuda.h>
#include <cuda_bf16.h>
#include <stdint.h>

#define DEVINL __device__ __forceinline__
#define MAPPING 1
#define REGS_GEMM 128
#define REGS_ATT 96
#define REGS_PROD 32
#define PREFETCH_W 1
#define PROXY_MODE 2

__device__ __forceinline__ void wgmma_ss_n128_tb1(float (&d)[64], uint64_t da, uint64_t db, int scale_d) {
  asm volatile("{\n.reg .pred p;\nsetp.ne.b32 p, %66, 0;\n"
    "wgmma.mma_async.sync.aligned.m64n128k16.f32.bf16.bf16 {%0, %1, %2, %3, %4, %5, %6, %7, %8, %9, %10, %11, %12, %13, %14, %15, %16, %17, %18, %19, %20, %21, %22, %23, %24, %25, %26, %27, %28, %29, %30, %31, %32, %33, %34, %35, %36, %37, %38, %39, %40, %41, %42, %43, %44, %45, %46, %47, %48, %49, %50, %51, %52, %53, %54, %55, %56, %57, %58, %59, %60, %61, %62, %63}, %64, %65, p, 1, 1, 0, 1;\n}\n"
    : "+f"(d[0]), "+f"(d[1]), "+f"(d[2]), "+f"(d[3]), "+f"(d[4]), "+f"(d[5]), "+f"(d[6]), "+f"(d[7]), "+f"(d[8]), "+f"(d[9]), "+f"(d[10]), "+f"(d[11]), "+f"(d[12]), "+f"(d[13]), "+f"(d[14]), "+f"(d[15]), "+f"(d[16]), "+f"(d[17]), "+f"(d[18]), "+f"(d[19]), "+f"(d[20]), "+f"(d[21]), "+f"(d[22]), "+f"(d[23]), "+f"(d[24]), "+f"(d[25]), "+f"(d[26]), "+f"(d[27]), "+f"(d[28]), "+f"(d[29]), "+f"(d[30]), "+f"(d[31]), "+f"(d[32]), "+f"(d[33]), "+f"(d[34]), "+f"(d[35]), "+f"(d[36]), "+f"(d[37]), "+f"(d[38]), "+f"(d[39]), "+f"(d[40]), "+f"(d[41]), "+f"(d[42]), "+f"(d[43]), "+f"(d[44]), "+f"(d[45]), "+f"(d[46]), "+f"(d[47]), "+f"(d[48]), "+f"(d[49]), "+f"(d[50]), "+f"(d[51]), "+f"(d[52]), "+f"(d[53]), "+f"(d[54]), "+f"(d[55]), "+f"(d[56]), "+f"(d[57]), "+f"(d[58]), "+f"(d[59]), "+f"(d[60]), "+f"(d[61]), "+f"(d[62]), "+f"(d[63])
    : "l"(da), "l"(db), "r"(scale_d));
}

__device__ __forceinline__ void wgmma_ss_n64_tb1(float (&d)[32], uint64_t da, uint64_t db, int scale_d) {
  asm volatile("{\n.reg .pred p;\nsetp.ne.b32 p, %34, 0;\n"
    "wgmma.mma_async.sync.aligned.m64n64k16.f32.bf16.bf16 {%0, %1, %2, %3, %4, %5, %6, %7, %8, %9, %10, %11, %12, %13, %14, %15, %16, %17, %18, %19, %20, %21, %22, %23, %24, %25, %26, %27, %28, %29, %30, %31}, %32, %33, p, 1, 1, 0, 1;\n}\n"
    : "+f"(d[0]), "+f"(d[1]), "+f"(d[2]), "+f"(d[3]), "+f"(d[4]), "+f"(d[5]), "+f"(d[6]), "+f"(d[7]), "+f"(d[8]), "+f"(d[9]), "+f"(d[10]), "+f"(d[11]), "+f"(d[12]), "+f"(d[13]), "+f"(d[14]), "+f"(d[15]), "+f"(d[16]), "+f"(d[17]), "+f"(d[18]), "+f"(d[19]), "+f"(d[20]), "+f"(d[21]), "+f"(d[22]), "+f"(d[23]), "+f"(d[24]), "+f"(d[25]), "+f"(d[26]), "+f"(d[27]), "+f"(d[28]), "+f"(d[29]), "+f"(d[30]), "+f"(d[31])
    : "l"(da), "l"(db), "r"(scale_d));
}

__device__ __forceinline__ void wgmma_ss_n32_tb1(float (&d)[16], uint64_t da, uint64_t db, int scale_d) {
  asm volatile("{\n.reg .pred p;\nsetp.ne.b32 p, %18, 0;\n"
    "wgmma.mma_async.sync.aligned.m64n32k16.f32.bf16.bf16 {%0, %1, %2, %3, %4, %5, %6, %7, %8, %9, %10, %11, %12, %13, %14, %15}, %16, %17, p, 1, 1, 0, 1;\n}\n"
    : "+f"(d[0]), "+f"(d[1]), "+f"(d[2]), "+f"(d[3]), "+f"(d[4]), "+f"(d[5]), "+f"(d[6]), "+f"(d[7]), "+f"(d[8]), "+f"(d[9]), "+f"(d[10]), "+f"(d[11]), "+f"(d[12]), "+f"(d[13]), "+f"(d[14]), "+f"(d[15])
    : "l"(da), "l"(db), "r"(scale_d));
}

__device__ __forceinline__ void wgmma_ss_n128_tb1_init(float (&d)[64], uint64_t da, uint64_t db) {
  asm volatile("{\n.reg .pred p;\nsetp.ne.b32 p, 0, 0;\n"
    "wgmma.mma_async.sync.aligned.m64n128k16.f32.bf16.bf16 {%0, %1, %2, %3, %4, %5, %6, %7, %8, %9, %10, %11, %12, %13, %14, %15, %16, %17, %18, %19, %20, %21, %22, %23, %24, %25, %26, %27, %28, %29, %30, %31, %32, %33, %34, %35, %36, %37, %38, %39, %40, %41, %42, %43, %44, %45, %46, %47, %48, %49, %50, %51, %52, %53, %54, %55, %56, %57, %58, %59, %60, %61, %62, %63}, %64, %65, p, 1, 1, 0, 1;\n}\n"
    : "=f"(d[0]), "=f"(d[1]), "=f"(d[2]), "=f"(d[3]), "=f"(d[4]), "=f"(d[5]), "=f"(d[6]), "=f"(d[7]), "=f"(d[8]), "=f"(d[9]), "=f"(d[10]), "=f"(d[11]), "=f"(d[12]), "=f"(d[13]), "=f"(d[14]), "=f"(d[15]), "=f"(d[16]), "=f"(d[17]), "=f"(d[18]), "=f"(d[19]), "=f"(d[20]), "=f"(d[21]), "=f"(d[22]), "=f"(d[23]), "=f"(d[24]), "=f"(d[25]), "=f"(d[26]), "=f"(d[27]), "=f"(d[28]), "=f"(d[29]), "=f"(d[30]), "=f"(d[31]), "=f"(d[32]), "=f"(d[33]), "=f"(d[34]), "=f"(d[35]), "=f"(d[36]), "=f"(d[37]), "=f"(d[38]), "=f"(d[39]), "=f"(d[40]), "=f"(d[41]), "=f"(d[42]), "=f"(d[43]), "=f"(d[44]), "=f"(d[45]), "=f"(d[46]), "=f"(d[47]), "=f"(d[48]), "=f"(d[49]), "=f"(d[50]), "=f"(d[51]), "=f"(d[52]), "=f"(d[53]), "=f"(d[54]), "=f"(d[55]), "=f"(d[56]), "=f"(d[57]), "=f"(d[58]), "=f"(d[59]), "=f"(d[60]), "=f"(d[61]), "=f"(d[62]), "=f"(d[63])
    : "l"(da), "l"(db));
}

__device__ __forceinline__ void wgmma_ss_n64_tb1_init(float (&d)[32], uint64_t da, uint64_t db) {
  asm volatile("{\n.reg .pred p;\nsetp.ne.b32 p, 0, 0;\n"
    "wgmma.mma_async.sync.aligned.m64n64k16.f32.bf16.bf16 {%0, %1, %2, %3, %4, %5, %6, %7, %8, %9, %10, %11, %12, %13, %14, %15, %16, %17, %18, %19, %20, %21, %22, %23, %24, %25, %26, %27, %28, %29, %30, %31}, %32, %33, p, 1, 1, 0, 1;\n}\n"
    : "=f"(d[0]), "=f"(d[1]), "=f"(d[2]), "=f"(d[3]), "=f"(d[4]), "=f"(d[5]), "=f"(d[6]), "=f"(d[7]), "=f"(d[8]), "=f"(d[9]), "=f"(d[10]), "=f"(d[11]), "=f"(d[12]), "=f"(d[13]), "=f"(d[14]), "=f"(d[15]), "=f"(d[16]), "=f"(d[17]), "=f"(d[18]), "=f"(d[19]), "=f"(d[20]), "=f"(d[21]), "=f"(d[22]), "=f"(d[23]), "=f"(d[24]), "=f"(d[25]), "=f"(d[26]), "=f"(d[27]), "=f"(d[28]), "=f"(d[29]), "=f"(d[30]), "=f"(d[31])
    : "l"(da), "l"(db));
}

__device__ __forceinline__ void wgmma_ss_n32_tb1_init(float (&d)[16], uint64_t da, uint64_t db) {
  asm volatile("{\n.reg .pred p;\nsetp.ne.b32 p, 0, 0;\n"
    "wgmma.mma_async.sync.aligned.m64n32k16.f32.bf16.bf16 {%0, %1, %2, %3, %4, %5, %6, %7, %8, %9, %10, %11, %12, %13, %14, %15}, %16, %17, p, 1, 1, 0, 1;\n}\n"
    : "=f"(d[0]), "=f"(d[1]), "=f"(d[2]), "=f"(d[3]), "=f"(d[4]), "=f"(d[5]), "=f"(d[6]), "=f"(d[7]), "=f"(d[8]), "=f"(d[9]), "=f"(d[10]), "=f"(d[11]), "=f"(d[12]), "=f"(d[13]), "=f"(d[14]), "=f"(d[15])
    : "l"(da), "l"(db));
}

__device__ __forceinline__ void wgmma_rs_n32_tb0(float (&d)[16], uint32_t a0, uint32_t a1, uint32_t a2, uint32_t a3, uint64_t db, int scale_d) {
  asm volatile("{\n.reg .pred p;\nsetp.ne.b32 p, %21, 0;\n"
    "wgmma.mma_async.sync.aligned.m64n32k16.f32.bf16.bf16 {%0, %1, %2, %3, %4, %5, %6, %7, %8, %9, %10, %11, %12, %13, %14, %15}, {%16, %17, %18, %19}, %20, p, 1, 1, 0;\n}\n"
    : "+f"(d[0]), "+f"(d[1]), "+f"(d[2]), "+f"(d[3]), "+f"(d[4]), "+f"(d[5]), "+f"(d[6]), "+f"(d[7]), "+f"(d[8]), "+f"(d[9]), "+f"(d[10]), "+f"(d[11]), "+f"(d[12]), "+f"(d[13]), "+f"(d[14]), "+f"(d[15])
    : "r"(a0), "r"(a1), "r"(a2), "r"(a3), "l"(db), "r"(scale_d));
}

__device__ __forceinline__ void wgmma_rs_n24_tb1(float (&d)[12], uint32_t a0, uint32_t a1, uint32_t a2, uint32_t a3, uint64_t db, int scale_d) {
  asm volatile("{\n.reg .pred p;\nsetp.ne.b32 p, %17, 0;\n"
    "wgmma.mma_async.sync.aligned.m64n24k16.f32.bf16.bf16 {%0, %1, %2, %3, %4, %5, %6, %7, %8, %9, %10, %11}, {%12, %13, %14, %15}, %16, p, 1, 1, 1;\n}\n"
    : "+f"(d[0]), "+f"(d[1]), "+f"(d[2]), "+f"(d[3]), "+f"(d[4]), "+f"(d[5]), "+f"(d[6]), "+f"(d[7]), "+f"(d[8]), "+f"(d[9]), "+f"(d[10]), "+f"(d[11])
    : "r"(a0), "r"(a1), "r"(a2), "r"(a3), "l"(db), "r"(scale_d));
}

__device__ __forceinline__ void wgmma_ss_n8_tb0(float (&d)[4], uint64_t da, uint64_t db, int scale_d) {
  asm volatile("{\n.reg .pred p;\nsetp.ne.b32 p, %6, 0;\n"
    "wgmma.mma_async.sync.aligned.m64n8k16.f32.bf16.bf16 {%0, %1, %2, %3}, %4, %5, p, 1, 1, 0, 0;\n}\n"
    : "+f"(d[0]), "+f"(d[1]), "+f"(d[2]), "+f"(d[3])
    : "l"(da), "l"(db), "r"(scale_d));
}

namespace {

constexpr int NCTA = 128;
constexpr int NTHREADS = 640;

constexpr uint32_t OFF_X = 0;
constexpr uint32_t OFF_B = 131072;
constexpr uint32_t OFF_K = 196608;
constexpr uint32_t OFF_V = 208896;
constexpr uint32_t OFF_K2 = 65536;
constexpr uint32_t OFF_V2 = 77824;
constexpr uint32_t OFF_G = 227328;
constexpr uint32_t OFF_BAR = 227840;
constexpr uint32_t OFF_Q0 = 228352;
constexpr uint32_t SMEM_USED = 232448;
constexpr uint32_t SMEM_BYTES = SMEM_USED;

enum : int {
  B_XFULL = 0, B_BFULL = 8, B_BEMPTY = 12, B_G2FULL = 16, B_G2EMPTY = 22, B_KFULL = 28, B_VFULL = 31, B_KEMPTY = 34,
  B_VEMPTY = 37, B_GATE = 40, B_QRDY = 41, B_REDFULL = 42, B_REDFREE = 43, B_GWFULL = 44,
  B_SIG = 45  , B_DUMMY = 51, B_QRDY2 = 52, B_K2FULL = 53  , B_KV2FREE = 59, B_COUNT = 60
};

__device__ __align__(1024) unsigned char g_K[32 * 2048 * 32];
__device__ __align__(1024) unsigned char g_V[32 * 2048 * 32];
__device__ __align__(1024) uint4 g_Q[32 * 32 * 128];
__device__ __align__(1024) unsigned char g_A2[16 * 72 * 8192];
constexpr int FL_KQ = 0  , FL_H = 128  , FL_O = 256  , FL_TICKET = 288;
__device__ __align__(1024) unsigned g_flags[(FL_TICKET + 2) * 32];

#define SPIN_LIMIT (1 << 18)

#define TS(idx) do {} while (0)
#define STG_TS(n, code) do { code; } while (0)
#define TSP(n) do {} while (0)
#define PROXY_W() do {} while (0)
#define PROXY_R() asm volatile("fence.proxy.async.global;" ::: "memory")
DEVINL uint32_t smem_u32(const void* p) { return (uint32_t)__cvta_generic_to_shared(p); }
DEVINL void mbar_init(uint32_t a, uint32_t c) { asm volatile("mbarrier.init.shared::cta.b64 [%0], %1;" ::"r"(a), "r"(c) : "memory"); }
DEVINL void mbar_expect(uint32_t a, uint32_t bytes) {
  asm volatile("mbarrier.arrive.expect_tx.shared::cta.b64 _, [%0], %1;" ::"r"(a), "r"(bytes) : "memory");
}
DEVINL void mbar_arrive(uint32_t a) { asm volatile("mbarrier.arrive.shared::cta.b64 _, [%0];" ::"r"(a) : "memory"); }
DEVINL bool mbar_test(uint32_t a, uint32_t parity) {
  uint32_t ok;
  asm volatile("{\n.reg .pred p;\nmbarrier.test_wait.parity.shared::cta.b64 p, [%1], %2;\nselp.u32 %0, 1, 0, p;\n}"
               : "=r"(ok) : "r"(a), "r"(parity) : "memory");
  return ok != 0;
}
DEVINL void mbar_wait(uint32_t a, uint32_t parity) {
  asm volatile(
      "{\n.reg .pred p;\n.reg .u32 c;\nmov.u32 c, 0;\n"
      "LW:\nmbarrier.try_wait.parity.shared::cta.b64 p, [%0], %1;\n@p bra LD;\n"
      "add.u32 c, c, 1;\nsetp.lt.u32 p, c, %2;\n@p bra LW;\nLD:\n}"
      ::"r"(a), "r"(parity), "n"(SPIN_LIMIT) : "memory");
}
DEVINL void mbar_wait_cluster(uint32_t a, uint32_t parity) {
  asm volatile(
      "{\n.reg .pred p;\n.reg .u32 c;\nmov.u32 c, 0;\n"
      "LW:\nmbarrier.try_wait.parity.acquire.cluster.shared::cta.b64 p, [%0], %1;\n@p bra LD;\n"
      "add.u32 c, c, 1;\nsetp.lt.u32 p, c, %2;\n@p bra LW;\nLD:\n}"
      ::"r"(a), "r"(parity), "n"(SPIN_LIMIT) : "memory");
}
DEVINL void mbar_wait2(uint32_t a, uint32_t pa, uint32_t b, uint32_t pb) {
  asm volatile(
      "{\n.reg .pred p, q;\n.reg .u32 c;\nmov.u32 c, 0;\n"
      "LW:\nmbarrier.try_wait.parity.shared::cta.b64 p, [%0], %1;\nmbarrier.try_wait.parity.shared::cta.b64 q, [%2], %3;\n"
      "and.pred p, p, q;\n@p bra LD;\n"
      "add.u32 c, c, 1;\nsetp.lt.u32 p, c, %4;\n@p bra LW;\nLD:\n}"
      ::"r"(a), "r"(pa), "r"(b), "r"(pb), "n"(SPIN_LIMIT) : "memory");
}
DEVINL void tma2d(uint32_t dst, const CUtensorMap* m, int c0, int c1, uint32_t bar) {
  asm volatile("cp.async.bulk.tensor.2d.shared::cluster.global.mbarrier::complete_tx::bytes [%0], [%1, {%3, %4}], [%2];"
               ::"r"(dst), "l"(m), "r"(bar), "r"(c0), "r"(c1) : "memory");
}
DEVINL void tma3d(uint32_t dst, const CUtensorMap* m, int c0, int c1, int c2, uint32_t bar) {
  asm volatile("cp.async.bulk.tensor.3d.shared::cluster.global.mbarrier::complete_tx::bytes [%0], [%1, {%3, %4, %5}], [%2];"
               ::"r"(dst), "l"(m), "r"(bar), "r"(c0), "r"(c1), "r"(c2) : "memory");
}
DEVINL void bulk_g2s(uint32_t dst, const void* src, uint32_t bytes, uint32_t bar) {
  asm volatile("cp.async.bulk.shared::cluster.global.mbarrier::complete_tx::bytes [%0], [%1], %2, [%3];"
               ::"r"(dst), "l"(src), "r"(bytes), "r"(bar) : "memory");
}
DEVINL void prefetch_l2(const void* src, uint32_t bytes) {
  asm volatile("cp.async.bulk.prefetch.L2.global [%0], %1;" ::"l"(src), "r"(bytes) : "memory");
}
DEVINL void prefetch_tmap(const CUtensorMap* m) { asm volatile("prefetch.tensormap [%0];" ::"l"(m) : "memory"); }
DEVINL void wg_fence() { asm volatile("wgmma.fence.sync.aligned;" ::: "memory"); }
DEVINL void wg_commit() { asm volatile("wgmma.commit_group.sync.aligned;" ::: "memory"); }
template <int N> DEVINL void wg_wait() { asm volatile("wgmma.wait_group.sync.aligned %0;" ::"n"(N) : "memory"); }
template <int N> DEVINL void fence_acc(float (&a)[N]) {
#pragma unroll
  for (int i = 0; i < N; i++) asm volatile("" : "+f"(a[i])::"memory");
}
template <int N> DEVINL void fence_u32(uint32_t (&a)[N]) {
#pragma unroll
  for (int i = 0; i < N; i++) asm volatile("" : "+r"(a[i])::"memory");
}
DEVINL uint64_t mkdesc(uint32_t addr, uint32_t lbo, uint32_t sbo, uint32_t swz) {
  return (uint64_t)((addr & 0x3FFFF) >> 4) | ((uint64_t)(lbo >> 4) << 16) | ((uint64_t)(sbo >> 4) << 32) | ((uint64_t)swz << 62);
}
DEVINL uint32_t pack_bf16(float lo, float hi) {
  uint32_t r;
  asm("cvt.rn.bf16x2.f32 %0, %1, %2;" : "=r"(r) : "f"(hi), "f"(lo));
  return r;
}
DEVINL uint32_t opaque(uint32_t x) { asm volatile("" : "+r"(x)); return x; }
DEVINL float ex2(float x) { float r; asm("ex2.approx.ftz.f32 %0, %1;" : "=f"(r) : "f"(x)); return r; }
DEVINL float rcp(float x) { float r; asm("rcp.approx.ftz.f32 %0, %1;" : "=f"(r) : "f"(x)); return r; }
DEVINL void stg32(void* p, uint32_t v) { asm volatile("st.global.u32 [%0], %1;" ::"l"(p), "r"(v) : "memory"); }
DEVINL unsigned ld_acquire(const unsigned* p) {
  unsigned v;
  asm volatile("ld.acquire.gpu.global.u32 %0, [%1];" : "=r"(v) : "l"(p) : "memory");
  return v;
}
DEVINL unsigned ld_relaxed(const unsigned* p) {
  unsigned v;
  asm volatile("ld.relaxed.gpu.global.u32 %0, [%1];" : "=r"(v) : "l"(p) : "memory");
  return v;
}
DEVINL void wait_flag(const unsigned* p, unsigned target) {
#pragma unroll 1
  for (int it = 0; it < SPIN_LIMIT; it++)
    if ((int)(ld_relaxed(p) - target) >= 0) break;
  ld_acquire(p);
  PROXY_R();
}
DEVINL unsigned* flag_ptr(int idx) { return g_flags + idx * 32; }

DEVINL void cta_coords(int b, int& i, int& j, int& i2, int& j2) {
  const int k = b >> 1;
  int G, s;
  if (k < 4) { G = 0; s = 4 + k; }
  else if (k < 36) { G = (k - 4) & 7; s = (k - 4) >> 3; }
  else { const int d = ((k - 36) * 37) >> 8; G = 1 + (k - 36) - 7 * d; s = 4 + d; }
  const int r = 2 * s + (b & 1);
  i2 = 4 * (G >> 1) + (r >> 2); j2 = 4 * (G & 1) + (r & 3);
  i = i2; j = j2;
}

constexpr float LOG2E = 1.4426950408889634f;

struct SiluPipe {
  float r[2];
  DEVINL void phase2(const float* a) {
    asm("tanh.approx.f32 %0, %1;" : "=f"(r[0]) : "f"(0.5f * a[0]));
    asm("tanh.approx.f32 %0, %1;" : "=f"(r[1]) : "f"(0.5f * a[1]));
  }
  DEVINL void phase3(const float* a, float s, unsigned char* dst) {
    const float h0 = a[0] * s, h1 = a[1] * s;
    stg32(dst, pack_bf16(fmaf(h0, r[0], h0), fmaf(h1, r[1], h1)));
  }
};

struct Desc { uint32_t a, b, b2; };
DEVINL Desc g1_desc(uint32_t sb_, int slot, int xkb0, int wg) {
  const uint32_t sb = opaque(sb_);
  Desc d;
  d.a = ((sb + OFF_X + xkb0 * 16384 + wg * 8192) & 0x3FFFF) >> 4 | 1u << 16;
  d.b = ((sb + OFF_B + slot * 16384) & 0x3FFFF) >> 4 | (8192u >> 4) << 16;
  d.b2 = 0;
  return d;
}
DEVINL int g2_phys(int i) { return i < 2 ? i : (i == 5 ? 2 : i + 1); }
DEVINL Desc g2_desc(uint32_t sb_, int slot, int wg, bool split) {
  const uint32_t sb = opaque(sb_);
  const int buf = g2_phys(slot);
  Desc d;
  d.a = ((sb + buf * 32768 + wg * 4096) & 0x3FFFF) >> 4 | (128u >> 4) << 16;
  d.b = ((sb + buf * 32768 + 16384) & 0x3FFFF) >> 4 | (split ? 4096u >> 4 : 8192u >> 4) << 16;
  d.b2 = d.b + (split ? 512 : 256);
  return d;
}
constexpr uint64_t DH_SW = (uint64_t)(1024 >> 4) << 32 | 1ull << 62;
constexpr uint64_t DH_A2 = (uint64_t)(512 >> 4) << 32;
template <int N, int KS, bool FIRST, class F, class G>
DEVINL bool g1_issue(float (&acc)[N / 2], Desc& d, G&& next, uint32_t nbar, uint32_t npar, uint32_t rel, F&& epi) {
  bool ok = false;
  const Desc c = d;
  wg_fence();
#pragma unroll
  for (int ks = 0; ks < KS; ks++) {
    const uint64_t da = DH_SW | (c.a + (((ks >> 2) * 16384 + (ks & 3) * 32) >> 4));
    const uint64_t db = DH_SW | (c.b + ((ks * 2048) >> 4));
    if (FIRST && ks == 0) {
      if constexpr (N == 128) wgmma_ss_n128_tb1_init(acc, da, db);
      if constexpr (N == 64) wgmma_ss_n64_tb1_init(acc, da, db);
      if constexpr (N == 32) wgmma_ss_n32_tb1_init(acc, da, db);
    } else {
      if constexpr (N == 128) wgmma_ss_n128_tb1(acc, da, db, 1);
      if constexpr (N == 64) wgmma_ss_n64_tb1(acc, da, db, 1);
      if constexpr (N == 32) wgmma_ss_n32_tb1(acc, da, db, 1);
    }
    if (ks == 1) { wg_commit(); wg_wait<1>(); if ((threadIdx.x & 31) == 0) mbar_arrive(rel); }
    if (ks == KS - 3) { ok = mbar_test(nbar, npar); d = next(); }
    epi(ks);
  }
  wg_commit();
  return ok;
}
template <bool FIRST, class F, class G>
DEVINL bool g2_issue(float (&acc)[64], Desc& d, G&& next, uint32_t nbar, uint32_t npar, uint32_t rel, F&& epi) {
  bool ok = false;
  const Desc c = d;
  wg_fence();
#pragma unroll
  for (int ks = 0; ks < 4; ks++) {
    const uint64_t da = DH_A2 | (c.a + (((ks >> 1) * 8192 + (ks & 1) * 256) >> 4));
    const uint64_t db = DH_SW | (((ks >> 1) ? c.b2 : c.b) + (ks & 1) * 128);
    if (FIRST && ks == 0) wgmma_ss_n128_tb1_init(acc, da, db);
    else wgmma_ss_n128_tb1(acc, da, db, 1);
    if (ks == 1) { wg_commit(); wg_wait<1>(); if ((threadIdx.x & 31) == 0) mbar_arrive(rel); }
    if (ks == 1) { ok = mbar_test(nbar, npar); d = next(); }
    epi(ks);
  }
  wg_commit();
  return ok;
}
template <int V> struct IC { static constexpr int value = V; };
struct NoEpi { DEVINL void operator()(int) const {} };

struct Maps {
  CUtensorMap x, qk, v, w1, w2, w2s, wo;
};

__global__ void __launch_bounds__(NTHREADS, 1)
fused_kernel(const __grid_constant__ Maps tm, const __nv_bfloat16* __restrict__ gate_w,
             const unsigned char* __restrict__ wqkv_raw, const unsigned char* __restrict__ w1_raw, const unsigned char* __restrict__ w2_raw,
             const unsigned char* __restrict__ wo_raw, __nv_bfloat16* __restrict__ out) {
  extern __shared__ __align__(1024) unsigned char smem_raw[];
  const uint32_t sb = smem_u32(smem_raw);
  unsigned char* sgen = smem_raw;
  const int tid = threadIdx.x, lane = tid & 31;
  const int warp = __shfl_sync(0xffffffffu, tid >> 5, 0);
  int bi, bj, bi2, bj2;
  cta_coords(blockIdx.x, bi, bj, bi2, bj2);
  auto BAR = [&](int idx) -> uint32_t { return sb + OFF_BAR + idx * 8; };

  if (warp >= 16) asm volatile("setmaxnreg.dec.sync.aligned.u32 %0;" ::"n"(REGS_PROD));
  if (lane == 0) {
    if (warp == 16) {
#pragma unroll
      for (int k = 0; k < 4; k++) mbar_init(BAR(B_BFULL + k), 1);
      asm volatile("fence.mbarrier_init.release.cluster;" ::: "memory");
      asm volatile("fence.proxy.async.shared::cta;" ::: "memory");
#pragma unroll
      for (int k = 0; k < 4; k++) {
        mbar_expect(BAR(B_BFULL + k), 16384);
        tma3d(sb + OFF_B + k * 16384, &tm.qk, 64 * bj, k * 64, 1, BAR(B_BFULL + k));
      }
    } else if (warp == 19) {
#pragma unroll
      for (int k = 0; k < 8; k++) mbar_init(BAR(B_XFULL + k), 1);
      asm volatile("fence.mbarrier_init.release.cluster;" ::: "memory");
      asm volatile("fence.proxy.async.shared::cta;" ::: "memory");
#pragma unroll
      for (int k = 0; k < 8; k++) {
        mbar_expect(BAR(B_XFULL + k), 16384);
        tma2d(sb + OFF_X + k * 16384, &tm.x, k * 64, bi * 128, BAR(B_XFULL + k));
      }
    } else if (warp == 17) {
      mbar_init(BAR(B_GWFULL), 1);
#pragma unroll
      for (int k = 0; k < 6; k++) { mbar_init(BAR(B_KFULL + k), 1); mbar_init(BAR(B_KEMPTY + k), 8); }
      asm volatile("fence.mbarrier_init.release.cluster;" ::: "memory");
      asm volatile("fence.proxy.async.shared::cta;" ::: "memory");
    } else if (warp == 18) {
#pragma unroll
      for (int k = 0; k < 4; k++) mbar_init(BAR(B_BEMPTY + k), 8);
#pragma unroll
      for (int k = 0; k < 6; k++) { mbar_init(BAR(B_G2FULL + k), 2); mbar_init(BAR(B_G2EMPTY + k), 8); mbar_init(BAR(B_SIG + k), k == 5 ? 16 : 8); mbar_init(BAR(B_K2FULL + k), 1); }
      mbar_init(BAR(B_DUMMY), 0xFFFFF); mbar_init(BAR(B_QRDY2), 8); mbar_init(BAR(B_KV2FREE), 8);
      mbar_init(BAR(B_GATE), 8); mbar_init(BAR(B_QRDY), 8); mbar_init(BAR(B_REDFULL), 1); mbar_init(BAR(B_REDFREE), 8);
      asm volatile("fence.mbarrier_init.release.cluster;" ::: "memory");
      asm volatile("fence.proxy.async.shared::cta;" ::: "memory");
      mbar_expect(BAR(B_REDFULL), 32768);
    }
  }
  __syncthreads();
  if (warp == 0) TS(15);
  asm volatile("barrier.cluster.arrive.relaxed.aligned;" ::: "memory");

  if (warp >= 16) {
   if (warp == 16) {
    if (lane == 0) {
      prefetch_tmap(&tm.v); prefetch_tmap(&tm.w1);
      prefetch_tmap(&tm.w2); prefetch_tmap(&tm.w2s); prefetch_tmap(&tm.wo);
#pragma unroll 1
      for (int n = 4; n < 8; n++) {
        mbar_wait(BAR(B_BEMPTY + n - 4), 0);
        TSP(170 + n);
        mbar_expect(BAR(B_BFULL + n - 4), 16384);
        tma3d(sb + OFF_B + (n - 4) * 16384, &tm.qk, 64 * bj, n * 64, 1, BAR(B_BFULL + n - 4));
      }
#pragma unroll 1
      for (int seg = 0; seg < 5; seg++) {
        const CUtensorMap* mp = seg ? &tm.w1 : &tm.v;
        const int col = seg ? 224 * bj + (seg == 1 ? 192 : 64 * (seg - 2)) : 64 * bj;
#pragma unroll 1
        for (int s = 0; s < 4; s++) {
          mbar_wait(BAR(B_BEMPTY + s), (seg + 1) & 1);
          TSP(178 + seg * 4 + s);
          mbar_expect(BAR(B_BFULL + s), 16384);
          tma2d(sb + OFF_B + s * 16384, mp, col, s * 128, BAR(B_BFULL + s));
        }
      }
      const int kh = bj2 & 1, c2 = bj2 & 6;
      int buf = 0, par = 0;
#pragma unroll 1
      for (int s = 0; s < 18; s++) {
        mbar_wait(BAR(B_G2EMPTY + buf), par);
        TSP(198 + s);
        const uint32_t dst = sb + g2_phys(buf) * 32768 + 16384, bar = BAR(B_G2FULL + buf);
        mbar_expect(bar, 16384);
        if (s < 2) {
          tma3d(dst, &tm.w2s, 0, 896 * kh + 448 * s + 192, c2, bar);
          tma3d(dst + 8192, &tm.w2s, 0, 896 * kh + 448 * s + 416, c2, bar);
        } else if (s < 14) tma3d(dst, &tm.w2, 0, 896 * kh + 224 * ((s - 2) & 3) + 64 * ((s - 2) >> 2), c2, bar);
        else tma3d(dst, &tm.wo, 0, 256 * kh + 64 * (s - 14), c2, bar);
        if (++buf == 6) { buf = 0; par ^= 1; }
      }
    }
  } else if (warp == 19) {
    if (lane == 0) {
      const unsigned ticket = atomicAdd(flag_ptr(FL_TICKET), 1u);
      const unsigned target = (ticket / NCTA + 1u) * 32u;
      const int kh = bj2 & 1;
      const unsigned char* a2 = g_A2 + (uint32_t)((bi2 * 2 + kh) * 36 * 8192);
      const unsigned* fh = flag_ptr(FL_H + (bi2 * 2 + kh) * 4);
      mbar_wait(BAR(B_SIG + 0), 0);
#pragma unroll 1
      for (int gq = 2; gq >= 0 && gq >= 2 - bi; gq--) wait_flag(flag_ptr(FL_KQ + (bi - 2 + gq) * 8 + bj), target >> 5);
      mbar_wait(BAR(B_KV2FREE), 0);
#pragma unroll 1
      for (int gq = 2; gq >= 0; gq--) {
        if (gq < 2 - bi) { mbar_arrive(BAR(B_K2FULL + gq)); mbar_arrive(BAR(B_K2FULL + 3 + gq)); continue; }
        const int goff = ((4 * bj + 3) * 16 + bi - 2 + gq) * 4096;
        mbar_expect(BAR(B_K2FULL + gq), 4096);
        bulk_g2s(sb + OFF_K2 + gq * 4096, g_K + goff, 4096, BAR(B_K2FULL + gq));
        mbar_expect(BAR(B_K2FULL + 3 + gq), 4096);
        bulk_g2s(sb + OFF_V2 + gq * 6144, g_V + goff, 4096, BAR(B_K2FULL + 3 + gq));
      }
      int buf = 0, par = 0;
#pragma unroll 1
      for (int s = 0; s < 18; s++) {
        if (s == 0 || (s & 3) == 2) {
          if (s != 14) mbar_wait(BAR(B_SIG + 1 + ((s + 2) >> 2)), 0);
          wait_flag((s == 14) ? flag_ptr(FL_O + bi2 * 2 + kh) : fh + ((s + 2) >> 2) * 32, target);
          TS(s == 14 ? 23 : s == 10 ? 31 : 20 + ((s + 2) >> 2));
        }
        mbar_wait(BAR(B_G2EMPTY + buf), par);
        TSP(222 + s);
        mbar_expect(BAR(B_G2FULL + buf), 16384);
        bulk_g2s(sb + g2_phys(buf) * 32768, a2 + s * 16384, 16384, BAR(B_G2FULL + buf));
        if (++buf == 6) { buf = 0; par ^= 1; }
      }
    }
  } else if (warp == 17) {
    if (lane == 0) {
      const unsigned ticket = atomicAdd(flag_ptr(FL_TICKET + 1), 1u);
      const unsigned target = ticket / NCTA + 1u;
      const int glive = 2 - bi;
      int goff = ((4 * bj) * 16 + bi - 2) * 4096;
      mbar_wait2(BAR(B_SIG + 0), 0, BAR(B_GATE), 0);
      asm volatile("fence.acq_rel.gpu;" ::: "memory");
      PROXY_R();
#pragma unroll 1
      for (int gq = 2; gq >= 0; gq--) {
        if (gq < glive) { mbar_arrive(BAR(B_KFULL + gq)); mbar_arrive(BAR(B_VFULL + gq)); continue; }
        if (gq < 2) wait_flag(flag_ptr(FL_KQ + (bi - 2 + gq) * 8 + bj), target);
        mbar_expect(BAR(B_KFULL + gq), 4096);
        bulk_g2s(sb + OFF_K + gq * 4096, g_K + (goff + gq * 4096), 4096, BAR(B_KFULL + gq));
        mbar_expect(BAR(B_VFULL + gq), 4096);
        bulk_g2s(sb + OFF_V + gq * 6144, g_V + (goff + gq * 4096), 4096, BAR(B_VFULL + gq));
      }
#pragma unroll 1
      for (int hh = 1; hh < 3; hh++) {
        goff += 65536;
#pragma unroll 1
        for (int r = 0; r < 6; r++) {
          const int e = (0x890 << 12 | 0x1A2) >> (4 * r) & 15;
          const int gq = e & 3, isv = e >> 3;
          mbar_wait(BAR(B_KEMPTY + isv * 3 + gq), (hh - 1) & 1);
          const uint32_t bar = BAR(B_KFULL + isv * 3 + gq);
          if (gq < glive) { mbar_arrive(bar); continue; }
          mbar_expect(bar, 4096);
          bulk_g2s(isv ? sb + OFF_V + gq * 6144 : sb + OFF_K + gq * 4096, (isv ? g_V : g_K) + (goff + gq * 4096), 4096, bar);
        }
      }
    }
  } else {
    if (lane == 0) {
#pragma unroll 1
      for (int r = 0; r < 4; r++) prefetch_l2(wqkv_raw + (size_t)(blockIdx.x * 4 + r) * 3072, 1024);
      prefetch_l2(w1_raw + (size_t)blockIdx.x * 14336, 14336);
      mbar_wait(BAR(B_XFULL + 7), 0);
      prefetch_l2(w2_raw + (size_t)blockIdx.x * 14336, 14336);
      prefetch_l2(wo_raw + (size_t)blockIdx.x * 4096, 4096);
#pragma unroll 1
      for (int sig = 0; sig < 6; sig++) {
        mbar_wait(BAR(B_SIG + sig), 0);
        const int f = (sig == 0) ? FL_KQ + bi * 8 + bj : (sig == 5) ? FL_O + bi * 2 + (bj >> 2) : FL_H + (bi * 2 + (bj >> 2)) * 4 + (sig - 1);
        PROXY_W();
        asm volatile("fence.acq_rel.gpu;" ::: "memory");
        asm volatile("red.relaxed.gpu.global.add.u32 [%0], %1;" ::"l"(flag_ptr(f)), "r"(sig < 1 ? 1u : 8u) : "memory");
        TS(sig ? 25 + sig : 24);
      }
    }
   }
    return;
  }

  const int wg = (warp >> 2) & 1, a = wg, w = warp & 3, g = lane >> 2, t = lane & 3;
  auto arrive = [&](int bar) { if (lane == 0) mbar_arrive(BAR(bar)); };
  if (warp < 8) {
    asm volatile("setmaxnreg.inc.sync.aligned.u32 %0;" ::"n"(REGS_GEMM));
    const int lane_off = lane * 4;
    float a1[64], a2[32], a3[16], a4[32], a5[32], a6[32];
    const int pp = bj & 3;
    const uint32_t hoff = ((bi * 2 + (bj >> 2)) * 36) * 8192 + (wg * 8 + w * 2) * 512;
    mbar_wait2(BAR(B_XFULL), 0, BAR(B_BFULL), 0);
    if (warp == 0) TS(0);
    Desc dsc = g1_desc(sb, 0, 0, wg);
    g1_issue<128, 4, true>(a1, dsc, [&] { return g1_desc(sb, 1, 1, wg); }, BAR(B_BFULL), 0, BAR(B_DUMMY), NoEpi());
    bool ok = false;
#pragma unroll 1
    for (int kb = 1; kb < 8; kb++) {
      STG_TS(kb, mbar_wait2(BAR(B_XFULL + kb), 0, BAR(B_BFULL + (kb & 3)), (kb >> 2) & 1));
      ok = g1_issue<128, 4, false>(a1, dsc, [&] { return g1_desc(sb, (kb + 1) & 3, (kb + 1) & 7, wg); }, BAR(B_BFULL + ((kb + 1) & 3)), ((kb + 1) >> 2) & 1,
                                   BAR(B_BEMPTY + ((kb - 1) & 3)), NoEpi());
    }
    if (warp == 0) TS(1);
#pragma unroll
    for (int s = 0; s < 2; s++) {
      STG_TS(8 + s, if (!ok) mbar_wait(BAR(B_BFULL + s), 0));
      auto epi = [&](int ks) {
        const int u = s * 8 + ks - 1;
        if (u == 0) fence_acc(a1);
        if (u >= 0 && u < 4) {
          unsigned char* p = g_K + (uint32_t)(((4 * bj + u) * 256 + (bi * 16 + wg * 8 + w * 2)) * 256 + opaque(lane_off));
          stg32(p, pack_bf16(a1[8 * u], a1[8 * u + 1]));
          stg32(p + 256, pack_bf16(a1[8 * u + 2], a1[8 * u + 3]));
          stg32(p + 128, pack_bf16(a1[8 * u + 4], a1[8 * u + 5]));
          stg32(p + 384, pack_bf16(a1[8 * u + 6], a1[8 * u + 7]));
        } else if (u >= 4 && u < 8) {
          unsigned char* p = g_V + (uint32_t)(((4 * bj + u - 4) * 16 + bi) * 4096 + (wg * 8 + w * 2) * 128 + opaque(lane_off));
          stg32(p, pack_bf16(a1[8 * u], a1[8 * u + 1]));
          stg32(p + 128, pack_bf16(a1[8 * u + 2], a1[8 * u + 3]));
          stg32(p + 2048, pack_bf16(a1[8 * u + 4], a1[8 * u + 5]));
          stg32(p + 2176, pack_bf16(a1[8 * u + 6], a1[8 * u + 7]));
          if (u == 7) { __syncwarp(); arrive(B_SIG + 0); }
        }
      };
      if (s == 0) ok = g1_issue<64, 8, true>(a2, dsc, [&] { return g1_desc(sb, (s + 1) & 3, 2 * ((s + 1) & 3), wg); }, BAR(B_BFULL + s + 1), 0, BAR(B_BEMPTY + ((s + 3) & 3)), epi);
      else ok = g1_issue<64, 8, false>(a2, dsc, [&] { return g1_desc(sb, (s + 1) & 3, 2 * ((s + 1) & 3), wg); }, BAR(B_BFULL + s + 1), 0, BAR(B_BEMPTY + ((s + 3) & 3)), epi);
    }
#pragma unroll 1
    for (int s = 2; s < 4; s++) {
      STG_TS(8 + s, if (!ok) mbar_wait(BAR(B_BFULL + s), 0));
      ok = g1_issue<64, 8, false>(a2, dsc, [&] { return g1_desc(sb, (s + 1) & 3, 2 * ((s + 1) & 3), wg); }, BAR(B_BFULL + ((s + 1) & 3)), s == 3 ? 1 : 0, BAR(B_BEMPTY + s - 1), NoEpi());
    }
    if (warp == 0) TS(2);
    {
      STG_TS(12, if (!ok) mbar_wait(BAR(B_BFULL), 1));
      auto epi = [&](int ks) {
        if (ks == 1) {
          fence_acc(a2);
          uint4 v;
          v.x = pack_bf16(a2[0], a2[1]); v.y = pack_bf16(a2[2], a2[3]);
          v.z = pack_bf16(a2[4], a2[5]); v.w = pack_bf16(a2[6], a2[7]);
          reinterpret_cast<uint4*>(sgen + OFF_Q0)[wg * 128 + w * 32 + opaque(lane)] = v;
          __syncwarp();
          arrive(B_QRDY);
        }
      };
      ok = g1_issue<32, 8, true>(a3, dsc, [&] { return g1_desc(sb, 1, 2, wg); }, BAR(B_BFULL + 1), 1, BAR(B_BEMPTY + 3), epi);
    }
#pragma unroll 1
    for (int s = 1; s < 3; s++) {
      STG_TS(12 + s, if (!ok) mbar_wait(BAR(B_BFULL + s), 1));
      ok = g1_issue<32, 8, false>(a3, dsc, [&] { return g1_desc(sb, (s + 1) & 3, 2 * ((s + 1) & 3), wg); }, BAR(B_BFULL + s + 1), 1, BAR(B_BEMPTY + s - 1), NoEpi());
    }
    {
      STG_TS(15, if (!ok) mbar_wait(BAR(B_BFULL + 3), 1));
      auto epi = [&](int ks) {
        const int u = ks - 4;
        if (u >= 0) {
          uint4 v;
          v.x = pack_bf16(a2[8 * u], a2[8 * u + 1]); v.y = pack_bf16(a2[8 * u + 2], a2[8 * u + 3]);
          v.z = pack_bf16(a2[8 * u + 4], a2[8 * u + 5]); v.w = pack_bf16(a2[8 * u + 6], a2[8 * u + 7]);
          g_Q[(uint32_t)(((bi * 2 + wg) * 32 + 4 * bj + u) * 128 + w * 32 + opaque(lane))] = v;
          if (u == 3) { __syncwarp(); arrive(B_QRDY2); }
        }
      };
      ok = g1_issue<32, 8, false>(a3, dsc, [&] { return g1_desc(sb, 0, 0, wg); }, BAR(B_BFULL), 0, BAR(B_BEMPTY + 2), epi);
    }
    if (warp == 0) TS(3);
    mbar_wait(BAR(B_GATE), 0);
    const float s0 = 0.5f - 0.5f * reinterpret_cast<const float*>(sgen + OFF_G)[wg * 64 + w * 16 + g];
    const float s1 = 0.5f - 0.5f * reinterpret_cast<const float*>(sgen + OFF_G)[wg * 64 + w * 16 + g + 8];
    SiluPipe sp;
    auto silu_step = [&](auto& src, int NP, int b, int pos, int sig) {
      const int d = b - 2;
      if (d >= 0 && d < NP) sp.phase3(&src[2 * d], (d & 1) ? s1 : s0,
                                      g_A2 + (hoff + opaque(lane_off) + (pos + (d >> 3)) * 8192 + ((d >> 1) & 3) * 128 + (d & 1) * 512));
      if (b >= 1 && b <= NP) sp.phase2(&src[2 * (b - 1)]);
      if (b == NP + 1) { __syncwarp(); arrive(B_SIG + sig); }
    };
#pragma unroll
    for (int s = 0; s < 4; s++) {
      STG_TS(16 + s, if (!ok) mbar_wait(BAR(B_BFULL + s), 0));
      auto epi = [&](int ks) {
        const int u = s * 8 + ks - 1;
        if (u == 0) fence_acc(a3);
        if (u >= 0 && u % 3 == 0) silu_step(a3, 8, u / 3, pp, 1);
      };
      if (s == 0) ok = g1_issue<64, 8, true>(a4, dsc, [&] { return g1_desc(sb, (s + 1) & 3, 2 * ((s + 1) & 3), wg); }, BAR(B_BFULL + ((s + 1) & 3)), s == 3 ? 1 : 0, BAR(B_BEMPTY + ((s + 3) & 3)), epi);
      else ok = g1_issue<64, 8, false>(a4, dsc, [&] { return g1_desc(sb, (s + 1) & 3, 2 * ((s + 1) & 3), wg); }, BAR(B_BFULL + ((s + 1) & 3)), s == 3 ? 1 : 0, BAR(B_BEMPTY + ((s + 3) & 3)), epi);
    }
    if (warp == 0) TS(4);
#pragma unroll
    for (int s = 0; s < 4; s++) {
      STG_TS(20 + s, if (!ok) mbar_wait(BAR(B_BFULL + s), 1));
      auto epi = [&](int ks) {
        const int u = s * 8 + ks - 1;
        if (u == 0) fence_acc(a4);
        if (u >= 0 && u % 3 != 2) silu_step(a4, 16, u - u / 3, 4 + 2 * pp, 2);
      };
      if (s == 0) ok = g1_issue<64, 8, true>(a5, dsc, [&] { return g1_desc(sb, (s + 1) & 3, 2 * ((s + 1) & 3), wg); }, BAR(B_BFULL + ((s + 1) & 3)), s == 3 ? 0 : 1, BAR(B_BEMPTY + ((s + 3) & 3)), epi);
      else ok = g1_issue<64, 8, false>(a5, dsc, [&] { return g1_desc(sb, (s + 1) & 3, 2 * ((s + 1) & 3), wg); }, BAR(B_BFULL + ((s + 1) & 3)), s == 3 ? 0 : 1, BAR(B_BEMPTY + ((s + 3) & 3)), epi);
    }
#pragma unroll
    for (int s = 0; s < 4; s++) {
      STG_TS(24 + s, if (!ok) mbar_wait(BAR(B_BFULL + s), 0));
      auto epi = [&](int ks) {
        const int u = s * 8 + ks - 1;
        if (s == 2 && ks == 1) arrive(B_G2EMPTY + 3);
        if (u == 0) fence_acc(a5);
        if (u >= 0 && u % 3 != 2) silu_step(a5, 16, u - u / 3, 12 + 2 * pp, 3);
      };
      const uint32_t nb = BAR(B_BFULL + ((s + 1) & 3)), rel = s == 0 ? BAR(B_BEMPTY + 3) : s == 3 ? BAR(B_KV2FREE) : BAR(B_G2EMPTY + s - 1);
      auto nxt = [&] { return g1_desc(sb, (s + 1) & 3, 2 * ((s + 1) & 3), wg); };
      if (s == 0) ok = g1_issue<64, 8, true>(a6, dsc, nxt, nb, 0, rel, epi);
      else ok = g1_issue<64, 8, false>(a6, dsc, nxt, nb, 0, rel, epi);
    }
    if (warp == 0) TS(5);
    mbar_wait(BAR(B_KV2FREE), 0);
    {
      uint32_t* vs = reinterpret_cast<uint32_t*>(sgen + OFF_V2);
#pragma unroll
      for (int gq = 0; gq < 3; gq++) { vs[gq * 1536 + 1024 + tid] = 0x3F803F80u; vs[gq * 1536 + 1280 + tid] = 0x3F803F80u; }
      if (bi < 2) {
        uint32_t* ks = reinterpret_cast<uint32_t*>(sgen + OFF_K2);
#pragma unroll 1
        for (int gq = 0; gq < 2 - bi; gq++) {
#pragma unroll
          for (int e = 0; e < 4; e++) { vs[gq * 1536 + e * 256 + tid] = 0; ks[gq * 1024 + e * 256 + tid] = 0; }
        }
      }
      asm volatile("fence.proxy.async.shared::cta;" ::: "memory");
    }
    wg_wait<0>();
    fence_acc(a6);
    arrive(B_G2EMPTY + 2);
    arrive(B_G2EMPTY + 4);
#pragma unroll
    for (int b = 0; b < 18; b++) silu_step(a6, 16, b, 20 + 2 * pp, 4);
    asm volatile("bar.sync 2, 256;" ::: "memory");
    asm volatile("setmaxnreg.dec.sync.aligned.u32 %0;" ::"n"(REGS_ATT));
  } else {
    asm volatile("setmaxnreg.inc.sync.aligned.u32 %0;" ::"n"(REGS_ATT));
    const int at = tid - 256;
    {
      uint4* gt = reinterpret_cast<uint4*>(sgen + OFF_K);
      gt[at] = make_uint4(0, 0, 0, 0);
      gt[at + 256] = make_uint4(0, 0, 0, 0);
      uint32_t* vs = reinterpret_cast<uint32_t*>(sgen + OFF_V);
#pragma unroll
      for (int gq = 0; gq < 3; gq++) { vs[gq * 1536 + 1024 + at] = 0x3F803F80u; vs[gq * 1536 + 1280 + at] = 0x3F803F80u; }
      asm volatile("bar.sync 1, 256;" ::: "memory");
      if (at < 64) gt[at * 8] = __ldg(reinterpret_cast<const uint4*>(gate_w) + at);
      asm volatile("fence.proxy.async.shared::cta;" ::: "memory");
      asm volatile("bar.sync 1, 256;" ::: "memory");
      float z[4] = {0.f, 0.f, 0.f, 0.f};
      fence_acc(z);
      const uint64_t dgb = mkdesc(sb + OFF_K, 128, 256, 0);
#pragma unroll 1
      for (int kb = 0; kb < 8; kb++) {
        mbar_wait(BAR(B_XFULL + kb), 0);
        const uint64_t dga = mkdesc(sb + OFF_X + kb * 16384 + a * 8192, 16, 1024, 1);
        wg_fence();
#pragma unroll
        for (int ks = 0; ks < 4; ks++) wgmma_ss_n8_tb0(z, dga + (uint64_t)(ks * 2), dgb + (uint64_t)((kb * 4 + ks) * 16), 1);
        wg_commit();
      }
      wg_wait<0>();
      fence_acc(z);
      if (t == 0) {
        float* gs = reinterpret_cast<float*>(sgen + OFF_G) + a * 64 + w * 16 + g;
        gs[0] = rcp(1.0f + ex2(-LOG2E * z[0]));
        gs[8] = rcp(1.0f + ex2(-LOG2E * z[2]));
      }
      asm volatile("bar.sync 1, 256;" ::: "memory");
      if (bi < 2) {
        uint32_t* ks = reinterpret_cast<uint32_t*>(sgen + OFF_K);
#pragma unroll 1
        for (int gq = 0; gq < 2 - bi; gq++) {
#pragma unroll
          for (int e = 0; e < 4; e++) { vs[gq * 1536 + e * 256 + at] = 0; ks[gq * 1024 + e * 256 + at] = 0; }
        }
        asm volatile("fence.proxy.async.shared::cta;" ::: "memory");
        asm volatile("bar.sync 1, 256;" ::: "memory");
      }
      __syncwarp();
      if (lane == 0) mbar_arrive(BAR(B_GATE));
    }
    if (warp == 8) TS(16);

  }

  {
    const int first_live = 4 - 2 * bi - a;
    const uint32_t qoff = ((bi * 2 + a) * 32 + 4 * bj) * 128 + (tid & 127);
    const uint32_t ooff = ((bi * 2 + (bj >> 2)) * 36 + 28 + 2 * (bj & 3)) * 8192 + (a * 8 + w * 2) * 512;
    constexpr float SC = 0.25f * LOG2E;
    constexpr float NEG_BIG = -3.0e38f;
    const float NEG_INF = __int_as_float(0xff800000);

    const bool grole = warp < 8;
    const int hbeg = grole ? 3 : 0, hend = grole ? 4 : 3;
    const uint32_t fb = grole ? BAR(B_K2FULL) : BAR(B_KFULL);
    const uint32_t eb = grole ? BAR(B_DUMMY) : BAR(B_KEMPTY), es = grole ? 0 : 8;
    mbar_wait(BAR(B_QRDY), 0);
    if (warp == 8) TS(17);
    uint32_t q[4], P[2][8];
    float O[12], S[2][16], n0 = 0.f, n1 = 0.f;
    {
      const uint4 v = grole ? __ldcg(g_Q + (qoff + 3 * 128)) : reinterpret_cast<const uint4*>(sgen + OFF_Q0)[tid & 255];
      q[0] = v.x; q[1] = v.y; q[2] = v.z; q[3] = v.w;
#pragma unroll
      for (int e = 0; e < 12; e++) O[e] = 0.f;
#pragma unroll
      for (int e = 0; e < 16; e++) { S[0][e] = 0.f; S[1][e] = 0.f; }
#pragma unroll
      for (int e = 0; e < 8; e++) { P[0][e] = 0u; P[1][e] = 0u; }
      fence_u32(P[0]);
      fence_u32(P[1]);
      fence_acc(O);
      fence_acc(S[0]);
      fence_acc(S[1]);
    }
    const uint32_t dk0 = ((sb + (grole ? OFF_K2 : OFF_K) + a * 2048) & 0x3FFFF) >> 4 | (128u >> 4) << 16;
    const uint32_t dv0 = ((sb + (grole ? OFF_V2 : OFF_V)) & 0x3FFFF) >> 4 | (128u >> 4) << 16;
    constexpr uint64_t DKH = (uint64_t)(256 >> 4) << 32, DVH = (uint64_t)(2048 >> 4) << 32;
    mbar_wait(fb + 16, 0);
    wg_fence();
    wgmma_rs_n32_tb0(S[0], q[0], q[1], q[2], q[3], DKH | (dk0 + 4 * 128), 0);
    wg_commit();
    if (warp == 8) TS(18);

    uint32_t bad = 0;
    auto finalize = [&](int head) {
      const uint32_t ln = opaque(lane);
      const float* gp = reinterpret_cast<const float*>(sgen + OFF_G) + a * 64 + w * 16 + (ln >> 2);
      const float f0 = gp[0] * rcp(O[8]), f1 = gp[8] * rcp(O[10]);
      const float o0 = O[0] * f0, o1 = O[1] * f0, o4 = O[4] * f0, o5 = O[5] * f0;
      const float o2 = O[2] * f1, o3 = O[3] * f1, o6 = O[6] * f1, o7 = O[7] * f1;
      constexpr float LIM = 1.0e36f;
      const bool ok0 = O[8] <= LIM && O[8] >= 1.0e-30f && fmaxf(fmaxf(fabsf(O[0]), fabsf(O[1])), fmaxf(fabsf(O[4]), fabsf(O[5]))) <= 3.0e38f && O[0] == O[0] && O[1] == O[1] && O[4] == O[4] && O[5] == O[5];
      const bool ok1 = O[10] <= LIM && O[10] >= 1.0e-30f && fmaxf(fmaxf(fabsf(O[2]), fabsf(O[3])), fmaxf(fabsf(O[6]), fabsf(O[7]))) <= 3.0e38f && O[2] == O[2] && O[3] == O[3] && O[6] == O[6] && O[7] == O[7];
      bad |= (ok0 ? 0u : 1u) << (2 * head) | (ok1 ? 0u : 2u) << (2 * head);
      unsigned char* p = g_A2 + (ooff + (head >> 1) * 8192 + (head & 1) * 256 + ln * 4);
      stg32(p, pack_bf16(o0, o1));
      stg32(p + 512, pack_bf16(o2, o3));
      stg32(p + 128, pack_bf16(o4, o5));
      stg32(p + 128 + 512, pack_bf16(o6, o7));
    };
    const int dlane = 16 * w + g - 2 * t;
    auto row_max = [&](const float (&Sx)[16], int dthr, bool isf, float& x0, float& x1) {
      x0 = NEG_BIG; x1 = NEG_BIG;
#pragma unroll
      for (int kk = 0; kk < 2; kk++) {
        const float* s = &Sx[8 * kk];
        const bool vA = (16 * kk <= dthr) != isf, vB = (16 * kk + 1 <= dthr) != isf;
        const bool vL = (16 * kk - 8 <= dthr) != isf, vH = (16 * kk + 8 <= dthr) != isf;
        x0 = fmaxf(x0, fmaxf(fmaxf(vA ? s[0] : NEG_INF, vB ? s[1] : NEG_INF), vH ? fmaxf(s[4], s[5]) : NEG_INF));
        x1 = fmaxf(x1, fmaxf(fmaxf(vA ? s[6] : NEG_INF, vB ? s[7] : NEG_INF), vL ? fmaxf(s[2], s[3]) : NEG_INF));
      }
      x0 = fmaxf(x0, __shfl_xor_sync(0xffffffffu, x0, 1));
      x1 = fmaxf(x1, __shfl_xor_sync(0xffffffffu, x1, 1));
      x0 = fmaxf(x0, __shfl_xor_sync(0xffffffffu, x0, 2));
      x1 = fmaxf(x1, __shfl_xor_sync(0xffffffffu, x1, 2));
    };
    auto exp_half = [&](auto mask_c, const float (&Sx)[16], uint32_t (&Px)[8], int dthr, bool isf, float c0, float c1) {
      constexpr bool MASK = decltype(mask_c)::value != 0;
#pragma unroll
      for (int kk = 0; kk < 2; kk++) {
        const float* s = &Sx[8 * kk];
        float a0 = c0, b0 = c0, h0 = c0, a1 = c1, b1 = c1, l1 = c1;
        if (MASK) {
          const bool vA = (16 * kk <= dthr) != isf, vB = (16 * kk + 1 <= dthr) != isf;
          const bool vL = (16 * kk - 8 <= dthr) != isf, vH = (16 * kk + 8 <= dthr) != isf;
          a0 = vA ? c0 : NEG_INF; b0 = vB ? c0 : NEG_INF; h0 = vH ? c0 : NEG_INF;
          a1 = vA ? c1 : NEG_INF; b1 = vB ? c1 : NEG_INF; l1 = vL ? c1 : NEG_INF;
        }
        Px[4 * kk] = pack_bf16(ex2(fmaf(s[0], SC, a0)), ex2(fmaf(s[1], SC, b0)));
        Px[4 * kk + 1] = pack_bf16(ex2(fmaf(s[2], SC, l1)), ex2(fmaf(s[3], SC, l1)));
        Px[4 * kk + 2] = pack_bf16(ex2(fmaf(s[4], SC, h0)), ex2(fmaf(s[5], SC, h0)));
        Px[4 * kk + 3] = pack_bf16(ex2(fmaf(s[6], SC, a1)), ex2(fmaf(s[7], SC, b1)));
      }
    };
    const uint32_t dvE = dv0 + (a ? 64 : 0), dvO = dv0 + (a ? 384 : 64);
    bool rdy = false;
    auto block = [&](auto hb_c, int hh) {
      constexpr int HB = decltype(hb_c)::value, x = HB & 1, c = 4 - HB / 2;
      constexpr int PB = (HB + 9) % 10, px = PB & 1, pc = 4 - PB / 2;
      constexpr int QB = (HB + 1) % 10, qc = 4 - QB / 2;
      constexpr bool isd = (c == 4), isf = (c == 0);
      const uint32_t par = grole ? 0 : hh & 1;
      const bool last = hh + 1 == hend;
      if ((HB & 1) && !rdy) {
        if (HB == 1) mbar_wait2(fb + 40, par, fb + 8, par);
        if (HB == 3) mbar_wait(fb + 32, par);
        if (HB == 5) mbar_wait(fb, par);
        if (HB == 7) mbar_wait(fb + 24, par);
        if (HB == 9) mbar_wait(last ? BAR(B_QRDY) : fb + 16, last ? 0 : par ^ 1);
      }
      if (HB == 6 && hh == 0) mbar_wait(BAR(B_QRDY2), 0);
      if (HB == 6) asm volatile("prefetch.global.L1 [%0];" ::"l"(g_Q + (qoff + (hh < 3 ? hh + 1 : 3) * 128)));
      wg_wait<0>();
      fence_acc(O);
      fence_acc(S[x]);
      fence_u32(P[x]);
      if (lane == 0) {
        if (HB == 3) mbar_arrive(eb + 2 * es);
        if (HB == 5) mbar_arrive(eb + 5 * es);
        if (HB == 7) mbar_arrive(eb + es);
        if (HB == 9) { mbar_arrive(eb); mbar_arrive(eb + 4 * es); }
        if (HB == 1) mbar_arrive(hh > hbeg ? eb + 3 * es : BAR(B_DUMMY));
      }
      if (HB == 1 && hh > hbeg) finalize(hh - 1);
      if (HB == 9) {
        const uint4 qn = __ldca(g_Q + (qoff + (hh < 3 ? hh + 1 : 3) * 128));
        q[0] = qn.x; q[1] = qn.y; q[2] = qn.z; q[3] = qn.w;
      }
      const bool live = c >= first_live;
      const int dthr = dlane - 32 * x;
      if (HB == 0) {
        float x0, x1;
        row_max(S[0], dthr, false, x0, x1);
        n0 = -x0 * SC; n1 = -x1 * SC;
      }
      const float c0 = live ? n0 : NEG_INF, c1 = live ? n1 : NEG_INF;
      const uint64_t dv = DVH | (((pc & 1) ? dvO : dvE) + (pc >> 1) * 384 + px * 32);
      wg_fence();
      wgmma_rs_n32_tb0(S[px], q[0], q[1], q[2], q[3], DKH | (dk0 + qc * 128 + px * 64), 0);
      wgmma_rs_n24_tb1(O, P[px][0], P[px][1], P[px][2], P[px][3], dv, PB == 0 ? 0 : 1);
      wgmma_rs_n24_tb1(O, P[px][4], P[px][5], P[px][6], P[px][7], dv + 16, 1);
      wg_commit();
      if (HB == 0) rdy = mbar_test(fb + 40, par) & mbar_test(fb + 8, par);
      if (HB == 2) rdy = mbar_test(fb + 32, par);
      if (HB == 4) rdy = mbar_test(fb, par);
      if (HB == 6) rdy = mbar_test(fb + 24, par);
      if (HB == 8) rdy = mbar_test(last ? BAR(B_QRDY) : fb + 16, last ? 0 : par ^ 1);
      if (HB == 1 || HB == 8) {
        if ((HB == 1) ? (w < 2) : (w >= 2)) {
#pragma unroll
          for (int e = 0; e < 8; e++) P[x][e] = 0u;
        } else {
          exp_half(IC<1>(), S[x], P[x], dthr, isf, c0, c1);
        }
      } else if (isd || isf) {
        exp_half(IC<1>(), S[x], P[x], dthr, isf, c0, c1);
      } else {
        exp_half(IC<0>(), S[x], P[x], 0, false, c0, c1);
      }
    };
#pragma unroll 1
    for (int hh = hbeg; hh < hend; hh++) {
      block(IC<0>(), hh); block(IC<1>(), hh);
      if (warp == 8) TS(32 + hh * 5);
      block(IC<2>(), hh); block(IC<3>(), hh);
      if (warp == 8) TS(33 + hh * 5);
      block(IC<4>(), hh); block(IC<5>(), hh);
      if (warp == 8) TS(34 + hh * 5);
      block(IC<6>(), hh); block(IC<7>(), hh);
      if (warp == 8) TS(35 + hh * 5);
      block(IC<8>(), hh); block(IC<9>(), hh);
      if (warp == 8) TS(36 + hh * 5);
    }
    wg_wait<0>();
    fence_acc(O);
    fence_acc(S[0]);
    wg_fence();
    wgmma_rs_n24_tb1(O, P[1][0], P[1][1], P[1][2], P[1][3], DVH | (dvE + 32), 1);
    wgmma_rs_n24_tb1(O, P[1][4], P[1][5], P[1][6], P[1][7], DVH | (dvE + 48), 1);
    wg_commit();
    wg_wait<0>();
    fence_acc(O);
    finalize(hend - 1);
    bad |= __shfl_xor_sync(0xffffffffu, bad, 1);
    bad |= __shfl_xor_sync(0xffffffffu, bad, 2);
#pragma unroll 1
    while (bad) {
      const int bit = __ffs(bad) - 1;
      bad &= bad - 1;
      const int head = bit >> 1, rh = bit & 1, gh = 4 * bj + head;
      const int row = bi * 128 + a * 64 + w * 16 + g + 8 * rh;
      float qv[16];
#pragma unroll
      for (int tt = 0; tt < 4; tt++) {
        const uint4 v = __ldcg(g_Q + (qoff - t + tt + head * 128));
        const uint32_t lo = rh ? v.y : v.x, hi = rh ? v.w : v.z;
        qv[2 * tt] = __uint_as_float(lo << 16); qv[2 * tt + 1] = __uint_as_float(lo & 0xffff0000u);
        qv[8 + 2 * tt] = __uint_as_float(hi << 16); qv[9 + 2 * tt] = __uint_as_float(hi & 0xffff0000u);
      }
      float m = NEG_INF, l = 0.f, acc4[4] = {0.f, 0.f, 0.f, 0.f};
#pragma unroll 1
      for (int key = max(row - 255, 0); key <= row; key++) {
        const unsigned char* kp = g_K + ((size_t)(gh * 256 + (key >> 3)) * 256 + (key & 7) * 16);
        float sc = 0.f;
#pragma unroll
        for (int dh = 0; dh < 2; dh++) {
          const uint4 kv = __ldcg(reinterpret_cast<const uint4*>(kp + dh * 128));
          const uint32_t ks[4] = {kv.x, kv.y, kv.z, kv.w};
#pragma unroll
          for (int e = 0; e < 4; e++) {
            sc = fmaf(qv[8 * dh + 2 * e], __uint_as_float(ks[e] << 16), sc);
            sc = fmaf(qv[8 * dh + 2 * e + 1], __uint_as_float(ks[e] & 0xffff0000u), sc);
          }
        }
        const float mn = fmaxf(m, sc);
        const float al = ex2((m - mn) * SC), pk = ex2((sc - mn) * SC);
        const unsigned char* vp = g_V + ((size_t)(gh * 16 + (key >> 7)) * 4096 + ((key >> 3) & 15) * 128 + (key & 7) * 16 + t * 4);
        const uint32_t v0 = __ldcg(reinterpret_cast<const uint32_t*>(vp)), v1 = __ldcg(reinterpret_cast<const uint32_t*>(vp + 2048));
        l = l * al + pk;
        acc4[0] = acc4[0] * al + pk * __uint_as_float(v0 << 16); acc4[1] = acc4[1] * al + pk * __uint_as_float(v0 & 0xffff0000u);
        acc4[2] = acc4[2] * al + pk * __uint_as_float(v1 << 16); acc4[3] = acc4[3] * al + pk * __uint_as_float(v1 & 0xffff0000u);
        m = mn;
      }
      const float f = reinterpret_cast<const float*>(sgen + OFF_G)[a * 64 + w * 16 + g + 8 * rh] * rcp(l);
      unsigned char* p = g_A2 + (ooff + (head >> 1) * 8192 + (head & 1) * 256 + rh * 512 + lane * 4);
      stg32(p, pack_bf16(acc4[0] * f, acc4[1] * f));
      stg32(p + 128, pack_bf16(acc4[2] * f, acc4[3] * f));
    }
    __syncwarp();
    arrive(B_SIG + 5);
    if (warp == 8) TS(19);
  }
  if (warp >= 8) return;

  {
    arrive(B_G2EMPTY + 5);
    asm volatile("setmaxnreg.inc.sync.aligned.u32 %0;" ::"n"(REGS_GEMM));
    float acc[64];
    Desc dsc = g2_desc(sb, 0, wg, true);
    if (warp == 0) TS(13);
    mbar_wait(BAR(B_G2FULL), 0);
    if (warp == 0) TS(6);
    bool ok = g2_issue<true>(acc, dsc, [&] { return g2_desc(sb, 1, wg, true); }, BAR(B_G2FULL + 1), 0, BAR(B_DUMMY), NoEpi());
    asm volatile("barrier.cluster.wait.acquire.aligned;" ::: "memory");
    const uint32_t peer = (blockIdx.x & 1) ^ 1;
    {
      int buf = 1, par = 0;
#pragma unroll 1
      for (int s = 1; s < 18; s++) {
        STG_TS(28 + s, if (!ok) mbar_wait(BAR(B_G2FULL + buf), par));
        if (warp == 0 && s == 6) TS(7);
        if (warp == 0 && s == 10) TS(8);
        if (warp == 0 && s == 14) TS(9);
        ok = g2_issue<false>(acc, dsc, [&] { return g2_desc(sb, buf == 5 ? 0 : buf + 1, wg, false); },
                             BAR(B_G2FULL + (buf == 5 ? 0 : buf + 1)), buf == 5 ? par ^ 1 : par,
                             s <= 12 ? BAR(B_G2EMPTY + (buf == 0 ? 5 : buf - 1)) : BAR(B_DUMMY), NoEpi());
        if (s == 13 && lane == 0) {
          uint32_t ra;
          asm volatile("mapa.shared::cluster.u32 %0, %1, %2;" : "=r"(ra) : "r"(BAR(B_REDFREE)), "r"(peer));
          asm volatile("mbarrier.arrive.relaxed.cluster.shared::cluster.b64 _, [%0];" ::"r"(ra) : "memory");
        }
        if (++buf == 6) { buf = 0; par ^= 1; }
      }
    }
    wg_wait<0>();
    fence_acc(acc);
    if (warp == 0) TS(10);
    const int kh = bj2 & 1;
    {
      uint32_t rbase, rbar;
      asm volatile("mapa.shared::cluster.u32 %0, %1, %2;" : "=r"(rbase) : "r"(sb + (uint32_t)(wg * 8 * 128 + w * 32 + opaque(lane)) * 16), "r"(peer));
      asm volatile("mapa.shared::cluster.u32 %0, %1, %2;" : "=r"(rbar) : "r"(BAR(B_REDFULL)), "r"(peer));
      mbar_wait_cluster(BAR(B_REDFREE), 0);
#pragma unroll
      for (int q = 0; q < 8; q++) {
        const float v0 = kh ? acc[4 * q] : acc[32 + 4 * q], v1 = kh ? acc[4 * q + 1] : acc[32 + 4 * q + 1];
        const float v2 = kh ? acc[4 * q + 2] : acc[32 + 4 * q + 2], v3 = kh ? acc[4 * q + 3] : acc[32 + 4 * q + 3];
        asm volatile("st.async.weak.shared::cluster.mbarrier::complete_tx::bytes.v4.f32 [%0], {%1, %2, %3, %4}, [%5];"
                     ::"r"(rbase + q * 2048), "f"(v0), "f"(v1), "f"(v2), "f"(v3), "r"(rbar) : "memory");
      }
    }
    mbar_wait_cluster(BAR(B_REDFULL), 0);
    if (warp == 0) TS(11);
    {
      const int ln = opaque(lane);
      const float4* rp = reinterpret_cast<const float4*>(sgen) + wg * 8 * 128 + w * 32 + ln;
      uint32_t lo[8], hi[8];
#pragma unroll
      for (int q = 0; q < 8; q++) {
        const float4 r = rp[q * 128];
        const float v0 = (kh ? acc[32 + 4 * q] : acc[4 * q]) + r.x, v1 = (kh ? acc[32 + 4 * q + 1] : acc[4 * q + 1]) + r.y;
        const float v2 = (kh ? acc[32 + 4 * q + 2] : acc[4 * q + 2]) + r.z, v3 = (kh ? acc[32 + 4 * q + 3] : acc[4 * q + 3]) + r.w;
        lo[q] = pack_bf16(v0, v1);
        hi[q] = pack_bf16(v2, v3);
      }
      const int row = bi2 * 128 + wg * 64 + w * 16 + (ln >> 2);
      __nv_bfloat16* op = out + (uint32_t)(row * 512 + (bj2 >> 1) * 128 + kh * 64 + (ln & 1) * 8 + ((ln >> 1) & 1) * 4);
      const bool odd = ln & 1;
#pragma unroll
      for (int q = 0; q < 8; q += 2) {
        const uint32_t yl = __shfl_xor_sync(0xffffffffu, odd ? lo[q] : lo[q + 1], 1);
        const uint32_t yh = __shfl_xor_sync(0xffffffffu, odd ? hi[q] : hi[q + 1], 1);
        const uint2 vl = odd ? make_uint2(yl, lo[q + 1]) : make_uint2(lo[q], yl);
        const uint2 vh = odd ? make_uint2(yh, hi[q + 1]) : make_uint2(hi[q], yh);
        *reinterpret_cast<uint2*>(op + q * 8) = vl;
        *reinterpret_cast<uint2*>(op + q * 8 + 8 * 512) = vh;
      }
    }
    if (warp == 0) TS(12);
  }
}

typedef CUresult (*EncodeFn)(CUtensorMap*, CUtensorMapDataType, cuuint32_t, void*, const cuuint64_t*, const cuuint64_t*,
                             const cuuint32_t*, const cuuint32_t*, CUtensorMapInterleave, CUtensorMapSwizzle,
                             CUtensorMapL2promotion, CUtensorMapFloatOOBfill);

void make_map2d(EncodeFn enc, CUtensorMap* m, const void* p, uint64_t cols, uint64_t rows, uint32_t bc, uint32_t br) {
  cuuint64_t gd[2] = {cols, rows};
  cuuint64_t gs[1] = {cols * 2};
  cuuint32_t bd[2] = {bc, br};
  cuuint32_t es[2] = {1, 1};
  enc(m, CU_TENSOR_MAP_DATA_TYPE_BFLOAT16, 2, const_cast<void*>(p), gd, gs, bd, es, CU_TENSOR_MAP_INTERLEAVE_NONE,
      CU_TENSOR_MAP_SWIZZLE_128B, CU_TENSOR_MAP_L2_PROMOTION_L2_128B, CU_TENSOR_MAP_FLOAT_OOB_FILL_NONE);
}
void make_map3d(EncodeFn enc, CUtensorMap* m, const void* p, uint64_t d0, uint64_t d1, uint64_t d2, uint64_t s1, uint64_t s2,
                uint32_t b1, uint32_t b2) {
  cuuint64_t gd[3] = {d0, d1, d2};
  cuuint64_t gs[2] = {s1, s2};
  cuuint32_t bd[3] = {64, b1, b2};
  cuuint32_t es[3] = {1, 1, 1};
  enc(m, CU_TENSOR_MAP_DATA_TYPE_BFLOAT16, 3, const_cast<void*>(p), gd, gs, bd, es, CU_TENSOR_MAP_INTERLEAVE_NONE,
      CU_TENSOR_MAP_SWIZZLE_128B, CU_TENSOR_MAP_L2_PROMOTION_L2_128B, CU_TENSOR_MAP_FLOAT_OOB_FILL_NONE);
}

}

extern "C" void kernel_launch(void* const* d_in, const int* in_sizes, int n_in, void* d_out, int out_size) {
  static EncodeFn enc = nullptr;
  if (!enc) {
    void* fn = nullptr;
    cudaDriverEntryPointQueryResult qr;
    cudaGetDriverEntryPoint("cuTensorMapEncodeTiled", &fn, cudaEnableDefault, &qr);
    enc = (EncodeFn)fn;
    cudaFuncSetAttribute(fused_kernel, cudaFuncAttributeMaxDynamicSharedMemorySize, SMEM_BYTES);
  }
  const void* x = d_in[0];
  const void* wqkv = d_in[1];
  const void* wo = d_in[2];
  const void* w1 = d_in[4];
  const void* w2 = d_in[5];
  const void* gate_w = d_in[6];
  Maps tm;
  make_map2d(enc, &tm.x, x, 512, 2048, 64, 128);
  make_map3d(enc, &tm.qk, wqkv, 512, 512, 3, 3072, 1024, 64, 2);
  make_map2d(enc, &tm.v, wqkv, 1536, 512, 64, 128);
  make_map2d(enc, &tm.w1, w1, 1792, 512, 64, 128);
  make_map3d(enc, &tm.w2, w2, 64, 1792, 8, 1024, 128, 64, 2);
  make_map3d(enc, &tm.w2s, w2, 64, 1792, 8, 1024, 128, 32, 2);
  make_map3d(enc, &tm.wo, wo, 64, 512, 8, 1024, 128, 64, 2);

  cudaLaunchConfig_t cfg = {};
  cfg.gridDim = dim3(NCTA);
  cfg.blockDim = dim3(NTHREADS);
  cfg.dynamicSmemBytes = SMEM_BYTES;
  cfg.stream = cudaStreamPerThread;
  cudaLaunchAttribute at[1];
  at[0].id = cudaLaunchAttributeClusterDimension;
  at[0].val.clusterDim.x = 2; at[0].val.clusterDim.y = 1; at[0].val.clusterDim.z = 1;
  cfg.attrs = at;
  cfg.numAttrs = 1;
  cudaLaunchKernelEx(&cfg, fused_kernel, tm, (const __nv_bfloat16*)gate_w,
                     (const unsigned char*)wqkv, (const unsigned char*)w1, (const unsigned char*)w2, (const unsigned char*)wo, (__nv_bfloat16*)d_out);
}
```
